```python
import torch

def _softmax(x, axis=-1):
    return torch.softmax(x, dim=axis)
def _gelu(x):
    return torch.nn.functional.gelu(x, approximate="tanh")
def _silu(x):
    return torch.nn.functional.silu(x)
def _sigmoid(x):
    return torch.sigmoid(x)
def _layernorm(x, axis=-1, eps=1e-5):
    m = x.mean(dim=axis, keepdim=True)
    v = x.var(dim=axis, keepdim=True, unbiased=False)
    return (x - m) / torch.sqrt(v + eps)
def _scatter_add(tgt, idx, src, axis=0):
    return tgt.clone().index_add_(axis, idx, src)
def _segment_sum(src, seg, n):
    out = torch.zeros((n,) + src.shape[1:], dtype=src.dtype)
    return out.index_add_(0, seg, src)
def _pad(x, pw):
    flat = tuple(v for pair in reversed(pw) for v in pair)
    return torch.nn.functional.pad(x, flat)

kernel_name = 'parallel_sum__gqa_block_cached__glu_gated_geglu__decode'

def setup_inputs():

    _w = (lambda a: (lambda t: t.to(torch.bfloat16) if t.is_floating_point() else t)(torch.as_tensor(a)))
    def _A_setup():
        B, Sq, D = 1, 1, 1024
        Hq, Hkv, Sk, Dh = 32, 4, 65536, 128
        assert Hq % Hkv == 0, (Hq, Hkv)
        return {
            "x": _w((lambda *s: torch.randn(*s, dtype=torch.bfloat16) * 0.05)(B, Sq, D)),
            "k_cache": _w((lambda *s: torch.randn(*s, dtype=torch.bfloat16) * 3.2)(B, Hkv, Sk, Dh)),
            "v_cache": _w((lambda *s: torch.randn(*s, dtype=torch.bfloat16) * 1.6)(B, Hkv, Sk, Dh)),
            "wq": _w((lambda *s: torch.randn(*s, dtype=torch.bfloat16) * 3.2)(D, Hq * Dh) * (D ** -0.5)),
            "wo": _w((lambda *s: torch.randn(*s, dtype=torch.bfloat16) * 1.6)(Hq * Dh, D) * ((Hq * Dh) ** -0.5)),
        }
    _A_in = _A_setup()

    def _B_setup():
        B, S, Dm, Df = 1, 1, 1024, 3584
        return {
            "x": _w((lambda *s: torch.randn(*s, dtype=torch.bfloat16) * 0.05)(B, S, Dm)),
            "w_gate": _w((lambda *s: torch.randn(*s, dtype=torch.bfloat16) * 1.6)(Dm, Df) * (Dm ** -0.5)),
            "w_up": _w((lambda *s: torch.randn(*s, dtype=torch.bfloat16) * 1.6)(Dm, Df) * (Dm ** -0.5)),
            "w_down": _w((lambda *s: torch.randn(*s, dtype=torch.bfloat16) * 1.6)(Df, Dm) * (Df ** -0.5)),
        }
    _B_in = _B_setup()

    return {
        "A_x": _A_in["x"],
        "A_k_cache": _A_in["k_cache"],
        "A_v_cache": _A_in["v_cache"],
        "A_wq": _A_in["wq"],
        "A_wo": _A_in["wo"],
        "B_x": _B_in["x"],
        "B_w_gate": _B_in["w_gate"],
        "B_w_up": _B_in["w_up"],
        "B_w_down": _B_in["w_down"],
    }

def reference(A_x, A_k_cache, A_v_cache, A_wq, A_wo, B_x, B_w_gate, B_w_up, B_w_down):
    def _A_ref(x, k_cache, v_cache, wq, wo):
        B, Sq, D = x.shape
        Hq, Dh = 32, 128
        Hkv = k_cache.shape[1]
        rep = Hq // Hkv
        q = (lambda x, *d: x.permute(*d))((x @ wq).reshape(B, Sq, Hq, Dh), 0, 2, 1, 3)
        k = (lambda x, n, axis: torch.repeat_interleave(x, n, dim=axis))(k_cache, rep, axis=1)
        v = (lambda x, n, axis: torch.repeat_interleave(x, n, dim=axis))(v_cache, rep, axis=1)
        scores = torch.einsum("bhqd,bhkd->bhqk", q, k) * (Dh ** -0.5)
        p = _softmax(scores, axis=-1)
        o = torch.einsum("bhqk,bhkd->bhqd", p, v)
        return (lambda x, *d: x.permute(*d))(o, 0, 2, 1, 3).reshape(B, Sq, Hq * Dh) @ wo

    def _B_ref(x, w_gate, w_up, w_down):
        g = torch.einsum("bsd,df->bsf", x, w_gate)
        u = torch.einsum("bsd,df->bsf", x, w_up)
        h = _gelu(g) * u
        return torch.einsum("bsf,fd->bsd", h, w_down)

    x = A_x
    xn = _layernorm(x, axis=-1)
    return x + _A_ref(xn, A_k_cache, A_v_cache, A_wq, A_wo) + _B_ref(xn, B_w_gate, B_w_up, B_w_down)
```

```cpp
#include <cuda_runtime.h>
#include <cuda_bf16.h>
#include <cuda.h>
#include <stdint.h>

namespace {

constexpr int D_MODEL = 1024;
constexpr int SK = 65536;
constexpr int HKV = 4;
constexpr int DFF = 3584;
constexpr int TILE_KEYS = 64;
constexpr int NTILES = HKV * SK / TILE_KEYS;
constexpr int TILES_PER_GROUP_LOG2 = 10;
constexpr int SLOT_BYTES = 16384;
#define CFG_NSLOTS 10
#define CFG_NINF 3
#define CFG_COMB_DELAY 6000
#define CFG_FFN_PRE 1
#define CFG_EARLY_POLL 0
#define CFG_LAST_DELAY 6500
#define CFG_PART_SLEEP 0
#define CFG_FIN_SLEEP 0
#define CFG_NFREE 2
constexpr int NFREE = CFG_NFREE;
constexpr int FFN_PRE = CFG_FFN_PRE;
constexpr int NSLOTS = CFG_NSLOTS;
constexpr int NINF = CFG_NINF;
constexpr int NCTA = 132;
constexpr int NQ_CTAS = 128;
constexpr int NF_CTAS = 112;
constexpr int NSTATIC = 2 * (NCTA - NQ_CTAS);
constexpr int NCONS = 128;
constexpr int NTHREADS = 192;
constexpr int QS_STRIDE = 68;
constexpr int RED_STRIDE = 132;
constexpr unsigned SPIN_LIMIT = 1u << 22;

constexpr int SM_RING = 0;
constexpr int SM_RED = SM_RING + NSLOTS * SLOT_BYTES;
constexpr int SM_XS = SM_RED + 4 * 8 * RED_STRIDE * 4;
constexpr int SM_QS = SM_XS + D_MODEL * 4;
constexpr int SM_SMALL = SM_QS + 32 * QS_STRIDE * 4;
constexpr int SM_SMALL_FLOATS = 448;
constexpr int SM_BAR = SM_SMALL + SM_SMALL_FLOATS * 4;
constexpr int SM_INFO = SM_BAR + (2 * NSLOTS + 8) * 8;
constexpr int SM_TOTAL = SM_INFO + (NSLOTS + 1) * 4;
constexpr int SMEM_BYTES = SM_TOTAL + 1024;

struct Params {
    CUtensorMap k, v, q, g, u;
    const __nv_bfloat16* x;
    const __nv_bfloat16* wo;
    const __nv_bfloat16* wd;
    __nv_bfloat16* out;
};

__device__ __align__(128) uint32_t g_q[2048];
__device__ __align__(128) uint32_t g_part[HKV * NQ_CTAS * NCTA * 8];
__device__ __align__(128) uint32_t g_fin[NQ_CTAS * NQ_CTAS * 8];
__device__ unsigned g_tile_ctr;
__device__ unsigned g_epoch;
#define STAMP_T(i, t) do {} while (0)
#define STAMP(i) STAMP_T(i, 0)

__device__ __forceinline__ uint32_t smem_u32(const void* p) { return (uint32_t)__cvta_generic_to_shared(p); }
__device__ __forceinline__ void mbar_init(uint32_t bar, uint32_t cnt) {
    asm volatile("mbarrier.init.shared::cta.b64 [%0], %1;" ::"r"(bar), "r"(cnt) : "memory");
}
__device__ __forceinline__ void mbar_expect_tx(uint32_t bar, uint32_t bytes) {
    asm volatile("mbarrier.arrive.expect_tx.shared::cta.b64 _, [%0], %1;" ::"r"(bar), "r"(bytes) : "memory");
}
__device__ __forceinline__ void mbar_arrive(uint32_t bar) {
    asm volatile("mbarrier.arrive.shared::cta.b64 _, [%0];" ::"r"(bar) : "memory");
}
__device__ __forceinline__ void mbar_wait(uint32_t bar, uint32_t parity) {
    uint32_t ok;
    unsigned it = 0;
    do {
        asm volatile(
            "{\n.reg .pred p;\n"
            "mbarrier.try_wait.parity.shared::cta.b64 p, [%1], %2;\n"
            "selp.u32 %0, 1, 0, p;\n}"
            : "=r"(ok) : "r"(bar), "r"(parity) : "memory");
        if (++it > SPIN_LIMIT) __trap();
    } while (!ok);
}
__device__ __forceinline__ unsigned globaltimer_lo() {
    unsigned t;
    asm volatile("mov.u32 %0, %globaltimer_lo;" : "=r"(t));
    return t;
}
__device__ __forceinline__ void bar_sync(int id, int n) { asm volatile("bar.sync %0, %1;" ::"r"(id), "r"(n) : "memory"); }
__device__ __forceinline__ void bar_arrive(int id, int n) { asm volatile("bar.arrive %0, %1;" ::"r"(id), "r"(n) : "memory"); }
__device__ __forceinline__ void cons_sync() { bar_sync(2, NCONS); }

__device__ __forceinline__ void tma3(const CUtensorMap* m, int row, uint32_t dst, uint32_t bar, uint64_t pol) {
    asm volatile(
        "cp.async.bulk.tensor.3d.shared::cluster.global.mbarrier::complete_tx::bytes.L2::cache_hint "
        "[%0], [%1, {%3, %4, %5}], [%2], %6;"
        ::"r"(dst), "l"(m), "r"(bar), "r"(0), "r"(row), "r"(0), "l"(pol) : "memory");
}
__device__ __forceinline__ void tma2(const CUtensorMap* m, int c0, int c1, uint32_t dst, uint32_t bar) {
    asm volatile(
        "cp.async.bulk.tensor.2d.shared::cluster.global.mbarrier::complete_tx::bytes [%0], [%1, {%3, %4}], [%2];"
        ::"r"(dst), "l"(m), "r"(bar), "r"(c0), "r"(c1) : "memory");
}
__device__ __forceinline__ void bulk1(const void* src, uint32_t dst, uint32_t bar, uint64_t pol) {
    asm volatile(
        "cp.async.bulk.shared::cluster.global.mbarrier::complete_tx::bytes.L2::cache_hint [%0], [%1], %2, [%3], %4;"
        ::"r"(dst), "l"(src), "r"(SLOT_BYTES), "r"(bar), "l"(pol) : "memory");
}
__device__ __forceinline__ uint4 ldg_stream(const void* p) {
    uint4 v;
    asm volatile("ld.global.nc.L1::no_allocate.L2::128B.v4.u32 {%0,%1,%2,%3}, [%4];"
                 : "=r"(v.x), "=r"(v.y), "=r"(v.z), "=r"(v.w) : "l"(p));
    return v;
}
__device__ __forceinline__ uint4 ld_relaxed4(const void* p) {
    uint4 v;
    asm volatile("ld.relaxed.gpu.global.v4.u32 {%0,%1,%2,%3}, [%4];"
                 : "=r"(v.x), "=r"(v.y), "=r"(v.z), "=r"(v.w) : "l"(p) : "memory");
    return v;
}
__device__ __forceinline__ uint2 ld_relaxed2(const void* p) {
    uint2 v;
    asm volatile("ld.relaxed.gpu.global.v2.u32 {%0,%1}, [%2];" : "=r"(v.x), "=r"(v.y) : "l"(p) : "memory");
    return v;
}
__device__ __forceinline__ void st_relaxed4(void* p, uint32_t a, uint32_t b, uint32_t c, uint32_t d) {
    asm volatile("st.relaxed.gpu.global.v4.u32 [%0], {%1,%2,%3,%4};" ::"l"(p), "r"(a), "r"(b), "r"(c), "r"(d) : "memory");
}
__device__ __forceinline__ void st_relaxed2(void* p, uint32_t a, uint32_t b) {
    asm volatile("st.relaxed.gpu.global.v2.u32 [%0], {%1,%2};" ::"l"(p), "r"(a), "r"(b) : "memory");
}
__device__ __forceinline__ void st_relaxed1(void* p, uint32_t a) {
    asm volatile("st.relaxed.gpu.global.u32 [%0], %1;" ::"l"(p), "r"(a) : "memory");
}
__device__ __forceinline__ bool nz4(const uint4& v) { return v.x != 0u && v.y != 0u && v.z != 0u && v.w != 0u; }
__device__ __forceinline__ uint32_t enc_bits(uint32_t b) { return b == 0u ? 0x80000000u : b; }
__device__ __forceinline__ uint32_t enc(float f, uint32_t tag) { return (__float_as_uint(f) & ~1u) | tag; }
__device__ __forceinline__ bool tag_ok4(const uint4& v, uint32_t tag) {
    return (((v.x ^ tag) | (v.y ^ tag) | (v.z ^ tag) | (v.w ^ tag)) & 1u) == 0u;
}
__device__ __forceinline__ bool tag_ok2(const uint2& v, uint32_t tag) { return (((v.x ^ tag) | (v.y ^ tag)) & 1u) == 0u; }

__device__ __forceinline__ uint4 lds128(uint32_t a) {
    uint4 v;
    asm volatile("ld.shared.v4.u32 {%0,%1,%2,%3}, [%4];" : "=r"(v.x), "=r"(v.y), "=r"(v.z), "=r"(v.w) : "r"(a) : "memory");
    return v;
}
__device__ __forceinline__ uint2 lds64(uint32_t a) {
    uint2 v;
    asm volatile("ld.shared.v2.u32 {%0,%1}, [%2];" : "=r"(v.x), "=r"(v.y) : "r"(a) : "memory");
    return v;
}
__device__ __forceinline__ void ldsm4(uint32_t (&r)[4], uint32_t a) {
    asm volatile("ldmatrix.sync.aligned.m8n8.x4.shared.b16 {%0,%1,%2,%3}, [%4];"
                 : "=r"(r[0]), "=r"(r[1]), "=r"(r[2]), "=r"(r[3]) : "r"(a) : "memory");
}
__device__ __forceinline__ void ldsm4t(uint32_t (&r)[4], uint32_t a) {
    asm volatile("ldmatrix.sync.aligned.m8n8.x4.trans.shared.b16 {%0,%1,%2,%3}, [%4];"
                 : "=r"(r[0]), "=r"(r[1]), "=r"(r[2]), "=r"(r[3]) : "r"(a) : "memory");
}
__device__ __forceinline__ void mma16816(float (&c)[4], const uint32_t (&a)[4], uint32_t b0, uint32_t b1) {
    asm volatile(
        "mma.sync.aligned.m16n8k16.row.col.f32.bf16.bf16.f32 {%0,%1,%2,%3}, {%4,%5,%6,%7}, {%8,%9}, {%0,%1,%2,%3};"
        : "+f"(c[0]), "+f"(c[1]), "+f"(c[2]), "+f"(c[3])
        : "r"(a[0]), "r"(a[1]), "r"(a[2]), "r"(a[3]), "r"(b0), "r"(b1));
}
__device__ __forceinline__ uint32_t movm(uint32_t a) {
    uint32_t d;
    asm volatile("movmatrix.sync.aligned.m8n8.trans.b16 %0, %1;" : "=r"(d) : "r"(a));
    return d;
}
__device__ __forceinline__ float bf_lo(uint32_t w) { return __uint_as_float(w << 16); }
__device__ __forceinline__ float bf_hi(uint32_t w) { return __uint_as_float(w & 0xffff0000u); }
__device__ __forceinline__ float bfr(float f) { return __bfloat162float(__float2bfloat16_rn(f)); }
__device__ __forceinline__ uint32_t pack_bf(float lo, float hi) {
    uint32_t r;
    asm("cvt.rn.bf16x2.f32 %0, %1, %2;" : "=r"(r) : "f"(hi), "f"(lo));
    return r;
}
__device__ __forceinline__ float ex2(float x) {
    float r;
    asm("ex2.approx.ftz.f32 %0, %1;" : "=f"(r) : "f"(x));
    return r;
}
__device__ __forceinline__ void fma8(float (&acc)[8], const uint4& w, float s) {
    acc[0] = fmaf(bf_lo(w.x), s, acc[0]); acc[1] = fmaf(bf_hi(w.x), s, acc[1]);
    acc[2] = fmaf(bf_lo(w.y), s, acc[2]); acc[3] = fmaf(bf_hi(w.y), s, acc[3]);
    acc[4] = fmaf(bf_lo(w.z), s, acc[4]); acc[5] = fmaf(bf_hi(w.z), s, acc[5]);
    acc[6] = fmaf(bf_lo(w.w), s, acc[6]); acc[7] = fmaf(bf_hi(w.w), s, acc[7]);
}
__device__ __forceinline__ void reduce_g8(float (&acc)[8]) {
#pragma unroll
    for (int o = 4; o <= 16; o <<= 1)
#pragma unroll
        for (int j = 0; j < 8; j++) acc[j] += __shfl_xor_sync(0xffffffffu, acc[j], o);
}

constexpr float LOG2E = 1.4426950408889634f;
constexpr float SM_SCALE = 0.08838834764831845f;
constexpr float M_EMPTY = -3.0e38f;

__global__ void __launch_bounds__(NTHREADS, 1) fused_decode_kernel(const __grid_constant__ Params P) {
    extern __shared__ uint8_t smem_raw[];
    uint8_t* sm = smem_raw + ((1024u - (smem_u32(smem_raw) & 1023u)) & 1023u);
    const uint32_t sb = smem_u32(sm);
    const int tid = threadIdx.x, lane = tid & 31, warp = tid >> 5;
    const int b = blockIdx.x;
    const uint32_t bar_full = sb + SM_BAR, bar_empty = bar_full + NSLOTS * 8;
    const uint32_t bar_flushed = bar_empty + NSLOTS * 8, bar_oready = bar_flushed + 32;
    volatile int* info = reinterpret_cast<volatile int*>(sm + SM_INFO);
    float* xs = reinterpret_cast<float*>(sm + SM_XS);
    float* small = reinterpret_cast<float*>(sm + SM_SMALL);
    float* hs = small;
    float* os = small + 32;
    float* tmp = small + 64;

    if (warp == 4) {
        unsigned nA = 0, nB = 0;
        if (lane == 0) {
            asm volatile("prefetch.tensormap [%0];" ::"l"(b < NQ_CTAS ? &P.q : &P.k) : "memory");
#pragma unroll
            for (int i = 0; i < NSLOTS; i++) {
                mbar_init(bar_full + 8 * i, 1);
                mbar_init(bar_empty + 8 * i, 4);
            }
#pragma unroll
            for (int i = 0; i < 8; i++) mbar_init(bar_flushed + 8 * i, 1);
            asm volatile("fence.mbarrier_init.release.cluster;" ::: "memory");
        }
        __syncwarp();
        bar_arrive(1, NTHREADS);
        if (lane == 0) {
            uint64_t pol;
            asm volatile("createpolicy.fractional.L2::evict_first.b64 %0, 1.0;" : "=l"(pol));
            int slot = 0, lag = 0, cnt = 0;
            uint32_t ph = 1, lag_ph = 0;
            auto acquire = [&](int tile_info, bool bounded) {
                mbar_wait(bar_empty + 8 * slot, ph);
                info[slot] = tile_info;
                mbar_expect_tx(bar_full + 8 * slot, SLOT_BYTES);
                if (cnt >= NINF && bounded) {
                    mbar_wait(bar_full + 8 * lag, lag_ph);
                    if (++lag == NSLOTS) { lag = 0; lag_ph ^= 1; }
                }
                cnt++;
            };
            auto advance = [&]() { if (++slot == NSLOTS) { slot = 0; ph ^= 1; } };
            if (b < NQ_CTAS) {
                const int npre = b < NF_CTAS ? 4 + 2 * FFN_PRE : 4;
#pragma unroll 1
                for (int i = 0; i < npre; i++) {
                    const CUtensorMap* mp = i < 4 ? &P.q : ((i & 1) ? &P.u : &P.g);
                    const int row = 256 * (i < 4 ? i : ((i - 4) >> 1));
                    acquire(0, true);
                    tma2(mp, 32 * b, row, sb + slot * SLOT_BYTES, bar_full + 8 * slot);
                    advance();
                    if (i == 0) {
                        asm volatile("prefetch.tensormap [%0];" ::"l"(&P.g) : "memory");
                        asm volatile("prefetch.tensormap [%0];" ::"l"(&P.u) : "memory");
                        asm volatile("prefetch.tensormap [%0];" ::"l"(&P.k) : "memory");
                        asm volatile("prefetch.tensormap [%0];" ::"l"(&P.v) : "memory");
                    }
                    if (i == npre - 3) {
                        nA = NSTATIC + atomicAdd(&g_tile_ctr, 1u);
                        nB = NSTATIC + atomicAdd(&g_tile_ctr, 1u);
                    }
                }
            } else {
                nA = b - NQ_CTAS;
                nB = nA + (NCTA - NQ_CTAS);
            }
            unsigned tA = globaltimer_lo(), tB = tA, tx;
            auto issue_tile = [&](unsigned t) {
                acquire((int)t, true);
                tma3(&P.k, (int)t * TILE_KEYS, sb + slot * SLOT_BYTES, bar_full + 8 * slot, pol);
                advance();
                acquire(0, true);
                tma3(&P.v, (int)t * TILE_KEYS, sb + slot * SLOT_BYTES, bar_full + 8 * slot, pol);
                advance();
            };
#pragma unroll 1
            while (true) {
                if (nA >= (unsigned)NTILES) { tx = tA - 10u * (nA - NTILES); break; }
                issue_tile(nA);
                tA = globaltimer_lo();
                nA = NSTATIC + atomicAdd(&g_tile_ctr, 1u);
                if (nB >= (unsigned)NTILES) { tx = tB - 10u * (nB - NTILES); break; }
                issue_tile(nB);
                tB = globaltimer_lo();
                nB = NSTATIC + atomicAdd(&g_tile_ctr, 1u);
            }
            info[NSLOTS] = (int)tx;
            auto tickets_back = [&]() {
                asm volatile("" : "+r"(nA), "+r"(nB));
                return (nA >= (unsigned)NTILES && nB >= (unsigned)NTILES) ? -1 : -2;
            };
            if (b >= NQ_CTAS) {
                mbar_wait(bar_empty + 8 * slot, ph);
                info[slot] = tickets_back();
                mbar_arrive(bar_full + 8 * slot);
            } else {
                constexpr int NGU = 2 * (4 - FFN_PRE);
#pragma unroll 1
                for (int j = b < NF_CTAS ? 0 : NGU + 4; j < NGU + 8; j++) {
                    const __nv_bfloat16* src = j < NGU + 4 ? P.wd + ((size_t)b * 32 + (j - NGU) * 8) * D_MODEL
                                                           : P.wo + ((size_t)(j - NGU - 4) * 1024 + b * 8) * D_MODEL;
                    int mark = -1;
                    if (j == NGU + 7) mark = tickets_back();
                    acquire(mark, j < NGU + 8 - NFREE);
                    if (j < NGU) tma2((j & 1) ? &P.u : &P.g, 32 * b, 256 * (FFN_PRE + (j >> 1)), sb + slot * SLOT_BYTES, bar_full + 8 * slot);
                    else bulk1(src, sb + slot * SLOT_BYTES, bar_full + 8 * slot, pol);
                    advance();
                }
            }
        }
        return;
    }

    STAMP(0);
    uint32_t tag;
    asm volatile("ld.relaxed.gpu.global.u32 %0, [%1];" : "=r"(tag) : "l"(&g_epoch) : "memory");
    tag = (tag & 1u) ^ 1u;

    if (warp == 5) {
        if (b >= NQ_CTAS) { bar_arrive(1, NTHREADS); return; }
        {
            uint4 xv[4];
#pragma unroll
            for (int i = 0; i < 4; i++) xv[i] = ldg_stream(P.x + (i * 32 + lane) * 8);
            float xf[32];
#pragma unroll
            for (int i = 0; i < 4; i++) {
                xf[8 * i + 0] = bf_lo(xv[i].x); xf[8 * i + 1] = bf_hi(xv[i].x);
                xf[8 * i + 2] = bf_lo(xv[i].y); xf[8 * i + 3] = bf_hi(xv[i].y);
                xf[8 * i + 4] = bf_lo(xv[i].z); xf[8 * i + 5] = bf_hi(xv[i].z);
                xf[8 * i + 6] = bf_lo(xv[i].w); xf[8 * i + 7] = bf_hi(xv[i].w);
            }
            float s = 0.f;
#pragma unroll
            for (int i = 0; i < 32; i++) s += xf[i];
#pragma unroll
            for (int o = 16; o; o >>= 1) s += __shfl_xor_sync(0xffffffffu, s, o);
            const float mean = s * (1.0f / D_MODEL);
            float vs = 0.f;
#pragma unroll
            for (int i = 0; i < 32; i++) { const float d = xf[i] - mean; vs = fmaf(d, d, vs); }
#pragma unroll
            for (int o = 16; o; o >>= 1) vs += __shfl_xor_sync(0xffffffffu, vs, o);
            const float mean_b = bfr(mean);
            const float var_b = bfr(vs * (1.0f / D_MODEL));
            const float den = bfr(__fsqrt_rn(bfr(var_b + 1e-5f)));
#pragma unroll
            for (int i = 0; i < 4; i++) {
                float y[8];
#pragma unroll
                for (int j = 0; j < 8; j++) y[j] = bfr(__fdiv_rn(bfr(xf[8 * i + j] - mean_b), den));
                float4* dst = reinterpret_cast<float4*>(xs + (i * 32 + lane) * 8);
                dst[0] = make_float4(y[0], y[1], y[2], y[3]);
                dst[1] = make_float4(y[4], y[5], y[6], y[7]);
            }
        }
        const uint2 xres = *reinterpret_cast<const uint2*>(P.x + b * 8 + (lane & 1) * 4);
        bar_sync(1, NTHREADS);

        const uint32_t* fsrc = g_fin + (size_t)b * NQ_CTAS * 8 + lane * 4;
        uint4 fv[8];
        unsigned fpend = 0xffu;
        auto poll_fin = [&]() {
#pragma unroll
            for (int i = 0; i < 8; i++)
                if (fpend & (1u << i)) fv[i] = ld_relaxed4(fsrc + i * 128);
#pragma unroll
            for (int i = 0; i < 8; i++)
                if (tag_ok4(fv[i], tag)) fpend &= ~(1u << i);
        };
#pragma unroll 1
        for (int g = 0; g < HKV; g++) {
            const uint32_t* pp = g_part + (size_t)(g * NQ_CTAS + b) * NCTA * 8 + lane * 4;
            uint4 pv[9];
            unsigned pend = lane < 2 * (NCTA - 128) ? 0x1ffu : 0x0ffu;
            pv[8] = make_uint4(0u, __float_as_uint(M_EMPTY), 0u, 0u);
            auto poll_part = [&]() {
#pragma unroll
                for (int i = 0; i < 9; i++)
                    if (pend & (1u << i)) pv[i] = ld_relaxed4(pp + i * 128);
#pragma unroll
                for (int i = 0; i < 9; i++)
                    if (tag_ok4(pv[i], tag)) pend &= ~(1u << i);
            };
            if (g == HKV - 1 && CFG_EARLY_POLL) poll_part();
            mbar_wait(bar_flushed + 8 * g, 0);
            {
                const unsigned t_start = g < HKV - 1 ? globaltimer_lo() : (unsigned)info[NSLOTS];
                if (g == HKV - 1) poll_fin();
                const unsigned delay = g < HKV - 1 ? CFG_COMB_DELAY : CFG_LAST_DELAY;
                while (globaltimer_lo() - t_start < delay) __nanosleep(100);
            }
            unsigned it = 0;
            while (true) {
                poll_part();
                if (pend == 0u) break;
                if (CFG_PART_SLEEP) __nanosleep(CFG_PART_SLEEP);
                if (++it > SPIN_LIMIT) __trap();
            }
            __syncwarp();
            if (g == 0 && lane < 16) g_q[16 * b + lane] = 0u;
            const bool odd = lane & 1;
            float M = M_EMPTY;
#pragma unroll
            for (int i = 0; i < 9; i++) M = fmaxf(M, odd ? __uint_as_float(pv[i].y) : M_EMPTY);
#pragma unroll
            for (int of = 16; of; of >>= 1) M = fmaxf(M, __shfl_xor_sync(0xffffffffu, M, of));
            float r[8], L = 0.f;
#pragma unroll
            for (int j = 0; j < 8; j++) r[j] = 0.f;
#pragma unroll
            for (int i = 0; i < 9; i++) {
                const float w = odd ? ex2((__uint_as_float(pv[i].y) - M) * LOG2E) : 0.f;
                L = fmaf(w, odd ? __uint_as_float(pv[i].z) : 0.f, L);
                const float c = __shfl_xor_sync(0xffffffffu, w * __uint_as_float(odd ? pv[i].x : 0u), 1);
                r[0] = fmaf(c, (float)((int)(pv[i].x << 16) >> 17), r[0]); r[1] = fmaf(c, (float)((int)(pv[i].x << 1) >> 17), r[1]);
                r[2] = fmaf(c, (float)((int)(pv[i].y << 16) >> 17), r[2]); r[3] = fmaf(c, (float)((int)(pv[i].y << 1) >> 17), r[3]);
                r[4] = fmaf(c, (float)((int)(pv[i].z << 16) >> 17), r[4]); r[5] = fmaf(c, (float)((int)(pv[i].z << 1) >> 17), r[5]);
                r[6] = fmaf(c, (float)((int)(pv[i].w << 16) >> 17), r[6]); r[7] = fmaf(c, (float)((int)(pv[i].w << 1) >> 17), r[7]);
            }
            const bool u16 = lane & 16, u8 = lane & 8, u4 = lane & 4;
#pragma unroll
            for (int j = 0; j < 4; j++) {
                const float send = u16 ? r[j] : r[j + 4], keep = u16 ? r[j + 4] : r[j];
                r[j] = keep + __shfl_xor_sync(0xffffffffu, send, 16);
            }
#pragma unroll
            for (int j = 0; j < 2; j++) {
                const float send = u8 ? r[j] : r[j + 2], keep = u8 ? r[j + 2] : r[j];
                r[j] = keep + __shfl_xor_sync(0xffffffffu, send, 8);
            }
            {
                const float send = u4 ? r[0] : r[1], keep = u4 ? r[1] : r[0];
                r[0] = keep + __shfl_xor_sync(0xffffffffu, send, 4);
            }
            r[0] += __shfl_xor_sync(0xffffffffu, r[0], 2);
#pragma unroll
            for (int of = 16; of; of >>= 1) L += __shfl_xor_sync(0xffffffffu, L, of);
            if ((lane & 3) == 0) os[g * 8 + (lane >> 2)] = bfr(r[0] / L);
            __syncwarp();
            if (lane == 0) mbar_arrive(bar_oready + 8 * g);
        }
        STAMP_T(8, 160);
        bar_sync(3, NCONS + 32);
        {
            unsigned it = 0;
            while (true) {
                poll_fin();
                if (fpend == 0u) break;
                if (CFG_FIN_SLEEP) __nanosleep(CFG_FIN_SLEEP);
                if (++it > SPIN_LIMIT) __trap();
            }
            __syncwarp();
            float r0 = 0.f, r1 = 0.f, r2 = 0.f, r3 = 0.f;
#pragma unroll
            for (int i = 0; i < 8; i++) {
                r0 += __uint_as_float(fv[i].x); r1 += __uint_as_float(fv[i].y);
                r2 += __uint_as_float(fv[i].z); r3 += __uint_as_float(fv[i].w);
            }
#pragma unroll
            for (int of = 2; of <= 16; of <<= 1) {
                r0 += __shfl_xor_sync(0xffffffffu, r0, of); r1 += __shfl_xor_sync(0xffffffffu, r1, of);
                r2 += __shfl_xor_sync(0xffffffffu, r2, of); r3 += __shfl_xor_sync(0xffffffffu, r3, of);
            }
            if (lane < 2) {
                const uint2 v = make_uint2(pack_bf(bf_lo(xres.x) + r0, bf_hi(xres.x) + r1),
                                           pack_bf(bf_lo(xres.y) + r2, bf_hi(xres.y) + r3));
                *reinterpret_cast<uint2*>(P.out + b * 8 + lane * 4) = v;
            }
            if (b == 0 && lane == 0) {
                g_tile_ctr = 0u;
                g_epoch = tag;
            }
        }
        STAMP_T(10, 160);
        return;
    }

    float* red = reinterpret_cast<float*>(sm + SM_RED);
    uint32_t* qs = reinterpret_cast<uint32_t*>(sm + SM_QS);
    const int g8 = lane >> 2, c4 = lane & 3;

    bar_sync(1, NTHREADS);
    STAMP(1);

    int slot = 0;
    uint32_t ph = 0;
    auto advance = [&]() { if (++slot == NSLOTS) { slot = 0; ph ^= 1; } };
    auto release = [&]() { __syncwarp(); if (lane == 0) mbar_arrive(bar_empty + 8 * slot); advance(); };
    auto box = [&](float (&acc)[8], int i) {
        float xr[8];
#pragma unroll
        for (int j = 0; j < 8; j++) xr[j] = xs[256 * i + 32 * j + (tid >> 2)];
        mbar_wait(bar_full + 8 * slot, ph);
#pragma unroll
        for (int j = 0; j < 8; j++) fma8(acc, lds128(sb + slot * SLOT_BYTES + j * 2048 + tid * 16), xr[j]);
        release();
    };

    if (b < NQ_CTAS) {
        float acc[8];
#pragma unroll
        for (int j = 0; j < 8; j++) acc[j] = 0.f;
#pragma unroll 1
        for (int i = 0; i < 4; i++) box(acc, i);
        STAMP(11);
        reduce_g8(acc);
        if (g8 == 0) {
#pragma unroll
            for (int j = 0; j < 8; j++) tmp[warp * 32 + c4 * 8 + j] = acc[j];
        }
        cons_sync();
        if (tid < 16) {
            const float* tq = tmp;
            const float q0 = tq[2 * tid] + tq[32 + 2 * tid] + tq[64 + 2 * tid] + tq[96 + 2 * tid];
            const float q1 = tq[2 * tid + 1] + tq[33 + 2 * tid] + tq[65 + 2 * tid] + tq[97 + 2 * tid];
            st_relaxed1(&g_q[16 * b + tid], enc_bits(pack_bf(q0, q1)));
        }
    }
    STAMP(2);

    float ag[8], au[8];
#pragma unroll
    for (int j = 0; j < 8; j++) { ag[j] = 0.f; au[j] = 0.f; }
    auto finish_hidden = [&]() {
        reduce_g8(ag);
        reduce_g8(au);
        if (g8 == 0) {
#pragma unroll
            for (int j = 0; j < 8; j++) {
                tmp[128 + warp * 32 + c4 * 8 + j] = ag[j];
                tmp[256 + warp * 32 + c4 * 8 + j] = au[j];
            }
        }
        cons_sync();
        if (tid < 32) {
            const float gg = bfr(tmp[128 + tid] + tmp[160 + tid] + tmp[192 + tid] + tmp[224 + tid]);
            const float uu = bfr(tmp[256 + tid] + tmp[288 + tid] + tmp[320 + tid] + tmp[352 + tid]);
            const float inner = 0.7978845608028654f * (gg + 0.044715f * gg * gg * gg);
            const float ge = bfr(0.5f * gg * (1.0f + tanhf(inner)));
            hs[tid] = bfr(ge * uu);
        }
    };
    if (b < NF_CTAS) {
#pragma unroll 1
        for (int i = 0; i < FFN_PRE; i++) { box(ag, i); box(au, i); }
        if (FFN_PRE == 4) finish_hidden();
    }
    STAMP(3);

    {
        uint4 qv[4];
        unsigned it = 0;
        while (true) {
#pragma unroll
            for (int i = 0; i < 4; i++) qv[i] = ld_relaxed4(&g_q[(i * NCONS + tid) * 4]);
            if (nz4(qv[0]) && nz4(qv[1]) && nz4(qv[2]) && nz4(qv[3])) break;
            if (++it > SPIN_LIMIT) __trap();
        }
#pragma unroll
        for (int i = 0; i < 4; i++) {
            const int w = (i * NCONS + tid) * 4;
            *reinterpret_cast<uint4*>(&qs[(w >> 6) * QS_STRIDE + (w & 63)]) = qv[i];
        }
        cons_sync();
    }
    STAMP(4);

    uint32_t qf[16];
    float o[8][4];
    float m0, m1, l0, l1;
    auto load_q = [&](int g) {
#pragma unroll
        for (int ks = 0; ks < 8; ks++) {
            qf[2 * ks] = qs[(g * 8 + g8) * QS_STRIDE + ks * 8 + c4];
            qf[2 * ks + 1] = qs[(g * 8 + g8) * QS_STRIDE + ks * 8 + 4 + c4];
        }
    };
    auto reset_acc = [&]() {
#pragma unroll
        for (int i = 0; i < 8; i++) { o[i][0] = 0.f; o[i][1] = 0.f; o[i][2] = 0.f; o[i][3] = 0.f; }
        m0 = M_EMPTY; m1 = M_EMPTY; l0 = 0.f; l1 = 0.f;
    };
    auto flush = [&](int g) {
#pragma unroll
        for (int of = 4; of <= 16; of <<= 1) {
            l0 += __shfl_xor_sync(0xffffffffu, l0, of);
            l1 += __shfl_xor_sync(0xffffffffu, l1, of);
        }
        cons_sync();
        float* rw = red + warp * 8 * RED_STRIDE;
#pragma unroll
        for (int i = 0; i < 8; i++) {
            rw[(2 * c4) * RED_STRIDE + 16 * i + g8] = o[i][0];
            rw[(2 * c4 + 1) * RED_STRIDE + 16 * i + g8] = o[i][1];
            rw[(2 * c4) * RED_STRIDE + 16 * i + 8 + g8] = o[i][2];
            rw[(2 * c4 + 1) * RED_STRIDE + 16 * i + 8 + g8] = o[i][3];
        }
        if (g8 == 0) {
            tmp[warp * 8 + 2 * c4] = m0; tmp[warp * 8 + 2 * c4 + 1] = m1;
            tmp[32 + warp * 8 + 2 * c4] = l0; tmp[32 + warp * 8 + 2 * c4 + 1] = l1;
        }
        cons_sync();
        const int h = tid >> 4, i16 = tid & 15;
        float mw[4], M = M_EMPTY;
#pragma unroll
        for (int w = 0; w < 4; w++) { mw[w] = tmp[w * 8 + h]; M = fmaxf(M, mw[w]); }
        float L = 0.f, r[8];
#pragma unroll
        for (int j = 0; j < 8; j++) r[j] = 0.f;
#pragma unroll
        for (int w = 0; w < 4; w++) {
            const float sc = ex2((mw[w] - M) * LOG2E);
            L = fmaf(sc, tmp[32 + w * 8 + h], L);
            const float4 a = *reinterpret_cast<const float4*>(red + (w * 8 + h) * RED_STRIDE + 4 * i16);
            const float4 c = *reinterpret_cast<const float4*>(red + (w * 8 + h) * RED_STRIDE + 64 + 4 * i16);
            r[0] = fmaf(sc, a.x, r[0]); r[1] = fmaf(sc, a.y, r[1]); r[2] = fmaf(sc, a.z, r[2]); r[3] = fmaf(sc, a.w, r[3]);
            r[4] = fmaf(sc, c.x, r[4]); r[5] = fmaf(sc, c.y, r[5]); r[6] = fmaf(sc, c.z, r[6]); r[7] = fmaf(sc, c.w, r[7]);
        }
        uint32_t* dst = g_part + ((size_t)(g * NQ_CTAS + h * 16 + (i16 >> 1)) * NCTA + b) * 8 + (i16 & 1) * 4;
#pragma unroll
        for (int k = 0; k < 2; k++) {
            float amax = fmaxf(fmaxf(fabsf(r[4 * k]), fabsf(r[4 * k + 1])), fmaxf(fabsf(r[4 * k + 2]), fabsf(r[4 * k + 3])));
            amax = fmaxf(amax, __shfl_xor_sync(0xffffffffu, amax, 1));
            const float inv = amax > 0.f ? 16383.f / amax : 0.f;
            const uint32_t w0 = ((uint32_t)(__float2int_rn(r[4 * k] * inv) & 0x7fff) << 1) |
                                ((uint32_t)(__float2int_rn(r[4 * k + 1] * inv) & 0x7fff) << 16) | tag;
            const uint32_t w1 = ((uint32_t)(__float2int_rn(r[4 * k + 2] * inv) & 0x7fff) << 1) |
                                ((uint32_t)(__float2int_rn(r[4 * k + 3] * inv) & 0x7fff) << 16) | tag;
            const uint32_t p0 = __shfl_xor_sync(0xffffffffu, w0, 1), p1 = __shfl_xor_sync(0xffffffffu, w1, 1);
            const bool o1 = i16 & 1;
            st_relaxed4(dst + (size_t)k * 8 * NCTA * 8,
                        o1 ? enc(amax * (1.f / 16383.f), tag) : w0, o1 ? enc(M, tag) : w1,
                        o1 ? enc(L, tag) : p0, o1 ? tag : p1);
        }
        if (tid == 0) mbar_arrive(bar_flushed + 8 * g);
        reset_acc();
    };

    int cur_g = 0;
    load_q(0);
    reset_acc();
    const int krow = warp * 16 + (lane & 7) + ((lane >> 3) & 1) * 8;
    const uint32_t k_off = krow * 128;
    const int k_hi = lane >> 4;
    const int vrow = warp * 16 + (lane & 7) + (lane >> 4) * 8;
    const uint32_t v_off = vrow * 128;
    const int v_hi = (lane >> 3) & 1;
    const int sw = lane & 7;
#pragma unroll 1
    while (true) {
        mbar_wait(bar_full + 8 * slot, ph);
        const int t = info[slot];
        if (t < 0) break;
        const int g = t >> TILES_PER_GROUP_LOG2;
        if (g != cur_g) {
            while (cur_g < g) { flush(cur_g); cur_g++; }
            load_q(g);
        }
        float sa[4] = {0.f, 0.f, 0.f, 0.f}, sc2[4] = {0.f, 0.f, 0.f, 0.f};
        {
            const uint32_t base = sb + slot * SLOT_BYTES + k_off;
            uint32_t a[8][4];
#pragma unroll
            for (int ks = 0; ks < 8; ks++)
                ldsm4(a[ks], base + (ks >> 2) * 8192 + ((((2 * ks) & 7) + k_hi) ^ sw) * 16);
#pragma unroll
            for (int ks = 0; ks < 8; ks += 2) {
                mma16816(sa, a[ks], qf[2 * ks], qf[2 * ks + 1]);
                mma16816(sc2, a[ks + 1], qf[2 * ks + 2], qf[2 * ks + 3]);
            }
        }
        release();
        float s[4];
#pragma unroll
        for (int j = 0; j < 4; j++) s[j] = bfr(bfr(sa[j] + sc2[j]) * SM_SCALE);
        float mx0 = fmaxf(s[0], s[2]), mx1 = fmaxf(s[1], s[3]);
        if (__any_sync(0xffffffffu, mx0 > m0 || mx1 > m1)) {
#pragma unroll
            for (int of = 4; of <= 16; of <<= 1) {
                mx0 = fmaxf(mx0, __shfl_xor_sync(0xffffffffu, mx0, of));
                mx1 = fmaxf(mx1, __shfl_xor_sync(0xffffffffu, mx1, of));
            }
            mx0 = fmaxf(mx0, m0);
            mx1 = fmaxf(mx1, m1);
            const float a0 = ex2((m0 - mx0) * LOG2E), a1 = ex2((m1 - mx1) * LOG2E);
            m0 = mx0; m1 = mx1;
            l0 *= a0; l1 *= a1;
#pragma unroll
            for (int i = 0; i < 8; i++) { o[i][0] *= a0; o[i][1] *= a1; o[i][2] *= a0; o[i][3] *= a1; }
        }
        const float p0 = ex2((s[0] - m0) * LOG2E), p1 = ex2((s[1] - m1) * LOG2E);
        const float p2 = ex2((s[2] - m0) * LOG2E), p3 = ex2((s[3] - m1) * LOG2E);
        l0 += p0 + p2;
        l1 += p1 + p3;
        const uint32_t pb0 = movm(pack_bf(p0, p1)), pb1 = movm(pack_bf(p2, p3));
        mbar_wait(bar_full + 8 * slot, ph);
        {
            const uint32_t base = sb + slot * SLOT_BYTES + v_off;
            uint32_t a[8][4];
#pragma unroll
            for (int mt = 0; mt < 8; mt++)
                ldsm4t(a[mt], base + (mt >> 2) * 8192 + ((((2 * mt) & 7) + v_hi) ^ sw) * 16);
#pragma unroll
            for (int mt = 0; mt < 8; mt++) mma16816(o[mt], a[mt], pb0, pb1);
        }
        release();
    }
    STAMP(5);
    while (cur_g < HKV) { flush(cur_g); cur_g++; }
    STAMP(6);
    if (b >= NQ_CTAS) return;

    float acc[8];
#pragma unroll
    for (int j = 0; j < 8; j++) acc[j] = 0.f;
    auto gemv_chunk = [&](const float* vec) {
        const float4 v0 = *reinterpret_cast<const float4*>(vec), v1 = *reinterpret_cast<const float4*>(vec + 4);
        const float vr[8] = {v0.x, v0.y, v0.z, v0.w, v1.x, v1.y, v1.z, v1.w};
        mbar_wait(bar_full + 8 * slot, ph);
        const uint32_t base = sb + slot * SLOT_BYTES + tid * 8;
#pragma unroll
        for (int r = 0; r < 8; r++) {
            const uint2 lo = lds64(base + r * 2048), hi = lds64(base + r * 2048 + 1024);
            fma8(acc, make_uint4(lo.x, lo.y, hi.x, hi.y), vr[r]);
        }
        advance();
    };
    if (b < NF_CTAS) {
        if (FFN_PRE < 4) {
#pragma unroll 1
            for (int i = FFN_PRE; i < 4; i++) { box(ag, i); box(au, i); }
            finish_hidden();
            cons_sync();
        }
#pragma unroll 1
        for (int i = 0; i < 4; i++) gemv_chunk(hs + 8 * i);
    }
    STAMP(7);
#pragma unroll 1
    for (int i = 0; i < 4; i++) {
        mbar_wait(bar_oready + 8 * i, 0);
        gemv_chunk(os + 8 * i);
    }
    STAMP(9);
    {
        uint32_t* d0 = g_fin + ((size_t)(tid >> 1) * NQ_CTAS + b) * 8 + (tid & 1) * 4;
        st_relaxed4(d0, enc(acc[0], tag), enc(acc[1], tag), enc(acc[2], tag), enc(acc[3], tag));
        st_relaxed4(d0 + (size_t)64 * NQ_CTAS * 8, enc(acc[4], tag), enc(acc[5], tag), enc(acc[6], tag), enc(acc[7], tag));
    }
    bar_arrive(3, NCONS + 32);
}

typedef CUresult (*EncodeFn)(CUtensorMap*, CUtensorMapDataType, cuuint32_t, void*, const cuuint64_t*, const cuuint64_t*,
                             const cuuint32_t*, const cuuint32_t*, CUtensorMapInterleave, CUtensorMapSwizzle,
                             CUtensorMapL2promotion, CUtensorMapFloatOOBfill);

void make_kv_map(EncodeFn enc_fn, CUtensorMap* m, void* p) {
    cuuint64_t gd[3] = {64, (cuuint64_t)HKV * SK, 2};
    cuuint64_t gs[2] = {256, 128};
    cuuint32_t bd[3] = {64, TILE_KEYS, 2};
    cuuint32_t es[3] = {1, 1, 1};
    enc_fn(m, CU_TENSOR_MAP_DATA_TYPE_BFLOAT16, 3, p, gd, gs, bd, es, CU_TENSOR_MAP_INTERLEAVE_NONE,
           CU_TENSOR_MAP_SWIZZLE_128B, CU_TENSOR_MAP_L2_PROMOTION_L2_256B, CU_TENSOR_MAP_FLOAT_OOB_FILL_NONE);
}
void make_w_map(EncodeFn enc_fn, CUtensorMap* m, void* p, int cols) {
    cuuint64_t gd[2] = {(cuuint64_t)cols, D_MODEL};
    cuuint64_t gs[1] = {(cuuint64_t)cols * 2};
    cuuint32_t bd[2] = {32, 256};
    cuuint32_t es[2] = {1, 1};
    enc_fn(m, CU_TENSOR_MAP_DATA_TYPE_BFLOAT16, 2, p, gd, gs, bd, es, CU_TENSOR_MAP_INTERLEAVE_NONE,
           CU_TENSOR_MAP_SWIZZLE_NONE, CU_TENSOR_MAP_L2_PROMOTION_L2_256B, CU_TENSOR_MAP_FLOAT_OOB_FILL_NONE);
}

}

extern "C" void kernel_launch(void* const* d_in, const int* in_sizes, int n_in, void* d_out, int out_size) {
    (void)in_sizes; (void)n_in; (void)out_size;
    static EncodeFn enc_fn = nullptr;
    if (!enc_fn) {
        cudaDriverEntryPointQueryResult qr;
        cudaGetDriverEntryPoint("cuTensorMapEncodeTiled", (void**)&enc_fn, cudaEnableDefault, &qr);
        cudaFuncSetAttribute(fused_decode_kernel, cudaFuncAttributeMaxDynamicSharedMemorySize, SMEM_BYTES);
    }
    Params P;
    make_kv_map(enc_fn, &P.k, d_in[1]);
    make_kv_map(enc_fn, &P.v, d_in[2]);
    make_w_map(enc_fn, &P.q, d_in[3], 4096);
    make_w_map(enc_fn, &P.g, d_in[6], DFF);
    make_w_map(enc_fn, &P.u, d_in[7], DFF);
    P.x = (const __nv_bfloat16*)d_in[0];
    P.wo = (const __nv_bfloat16*)d_in[4];
    P.wd = (const __nv_bfloat16*)d_in[8];
    P.out = (__nv_bfloat16*)d_out;
    void* args[] = {&P};
    cudaLaunchCooperativeKernel((const void*)fused_decode_kernel, dim3(NCTA), dim3(NTHREADS), args, SMEM_BYTES,
                                cudaStreamPerThread);
}
```

```cpp
#include <cuda_runtime.h>
#include <cuda_bf16.h>
#include <cuda.h>
#include <stdint.h>

namespace {

constexpr int D_MODEL = 1024;
constexpr int SK = 65536;
constexpr int HKV = 4;
constexpr int DFF = 3584;
constexpr int TILE_KEYS = 64;
constexpr int NTILES = HKV * SK / TILE_KEYS;
constexpr int TILES_PER_GROUP_LOG2 = 10;
constexpr int SLOT_BYTES = 16384;
constexpr int NSLOTS = 10;
constexpr int NINF = 3;
constexpr int FFN_PRE = 3;
constexpr int LAST_G = 1;
constexpr int FIN_G = 2;
constexpr unsigned COMB_DELAY_NS = 6000;
constexpr unsigned LAST_DELAY_NS = 5000;
constexpr int NCTA = 132;
constexpr int NQ_CTAS = 128;
constexpr int NF_CTAS = 112;
constexpr int NSTATIC = 2 * (NCTA - NQ_CTAS);
constexpr int NCONS = 128;
constexpr int NTHREADS = 192;
constexpr int QS_STRIDE = 68;
constexpr int RED_STRIDE = 132;
constexpr unsigned SPIN_LIMIT = 1u << 20;

constexpr int SM_RING = 0;
constexpr int SM_RED = SM_RING + NSLOTS * SLOT_BYTES;
constexpr int SM_XS = SM_RED + 4 * 8 * RED_STRIDE * 4;
constexpr int SM_QS = SM_XS + D_MODEL * 4;
constexpr int SM_SMALL = SM_QS + 32 * QS_STRIDE * 4;
constexpr int SM_SMALL_FLOATS = 448;
constexpr int SM_BAR = SM_SMALL + SM_SMALL_FLOATS * 4;
constexpr int SM_INFO = SM_BAR + (2 * NSLOTS + 8) * 8;
constexpr int SM_TOTAL = SM_INFO + (NSLOTS + 1) * 4;
constexpr int SMEM_BYTES = SM_TOTAL + 1024;

struct Params {
    CUtensorMap k, v, q, g, u;
    const __nv_bfloat16* x;
    const __nv_bfloat16* wo;
    const __nv_bfloat16* wd;
    __nv_bfloat16* out;
};

__device__ __align__(128) uint32_t g_q[2048];
__device__ __align__(128) uint32_t g_part[HKV * NQ_CTAS * NCTA * 8];
__device__ __align__(32) unsigned g_state[8];

__device__ __forceinline__ uint32_t smem_u32(const void* p) { return (uint32_t)__cvta_generic_to_shared(p); }
__device__ __forceinline__ void mbar_init(uint32_t bar, uint32_t cnt) {
    asm volatile("mbarrier.init.shared::cta.b64 [%0], %1;" ::"r"(bar), "r"(cnt) : "memory");
}
__device__ __forceinline__ void mbar_expect_tx(uint32_t bar, uint32_t bytes) {
    asm volatile("mbarrier.arrive.expect_tx.shared::cta.b64 _, [%0], %1;" ::"r"(bar), "r"(bytes) : "memory");
}
__device__ __forceinline__ void mbar_arrive(uint32_t bar) {
    asm volatile("mbarrier.arrive.shared::cta.b64 _, [%0];" ::"r"(bar) : "memory");
}
__device__ __forceinline__ void mbar_wait(uint32_t bar, uint32_t parity) {
    uint32_t ok;
    unsigned it = 0;
    do {
        asm volatile(
            "{\n.reg .pred p;\n"
            "mbarrier.try_wait.parity.shared::cta.b64 p, [%1], %2;\n"
            "selp.u32 %0, 1, 0, p;\n}"
            : "=r"(ok) : "r"(bar), "r"(parity) : "memory");
        if (++it > SPIN_LIMIT) __trap();
    } while (!ok);
}
__device__ __forceinline__ unsigned globaltimer_lo() {
    unsigned t;
    asm volatile("mov.u32 %0, %globaltimer_lo;" : "=r"(t));
    return t;
}
__device__ __forceinline__ void bar_sync(int id, int n) { asm volatile("bar.sync %0, %1;" ::"r"(id), "r"(n) : "memory"); }
__device__ __forceinline__ void bar_arrive(int id, int n) { asm volatile("bar.arrive %0, %1;" ::"r"(id), "r"(n) : "memory"); }
__device__ __forceinline__ void cons_sync() { bar_sync(2, NCONS); }

__device__ __forceinline__ void tma3(const CUtensorMap* m, int row, uint32_t dst, uint32_t bar, uint64_t pol) {
    asm volatile(
        "cp.async.bulk.tensor.3d.shared::cluster.global.mbarrier::complete_tx::bytes.L2::cache_hint "
        "[%0], [%1, {%3, %4, %5}], [%2], %6;"
        ::"r"(dst), "l"(m), "r"(bar), "r"(0), "r"(row), "r"(0), "l"(pol) : "memory");
}
__device__ __forceinline__ void tma2(const CUtensorMap* m, int c0, int c1, uint32_t dst, uint32_t bar) {
    asm volatile(
        "cp.async.bulk.tensor.2d.shared::cluster.global.mbarrier::complete_tx::bytes [%0], [%1, {%3, %4}], [%2];"
        ::"r"(dst), "l"(m), "r"(bar), "r"(c0), "r"(c1) : "memory");
}
__device__ __forceinline__ void bulk1(const void* src, uint32_t dst, uint32_t bar, uint64_t pol) {
    asm volatile(
        "cp.async.bulk.shared::cluster.global.mbarrier::complete_tx::bytes.L2::cache_hint [%0], [%1], %2, [%3], %4;"
        ::"r"(dst), "l"(src), "r"(SLOT_BYTES), "r"(bar), "l"(pol) : "memory");
}
__device__ __forceinline__ uint4 ldg_stream(const void* p) {
    uint4 v;
    asm volatile("ld.global.nc.L1::no_allocate.L2::128B.v4.u32 {%0,%1,%2,%3}, [%4];"
                 : "=r"(v.x), "=r"(v.y), "=r"(v.z), "=r"(v.w) : "l"(p));
    return v;
}
__device__ __forceinline__ uint4 ld_relaxed4(const void* p) {
    uint4 v;
    asm volatile("ld.relaxed.gpu.global.v4.u32 {%0,%1,%2,%3}, [%4];"
                 : "=r"(v.x), "=r"(v.y), "=r"(v.z), "=r"(v.w) : "l"(p) : "memory");
    return v;
}
__device__ __forceinline__ void st_relaxed4(void* p, uint32_t a, uint32_t b, uint32_t c, uint32_t d) {
    asm volatile("st.relaxed.gpu.global.v4.u32 [%0], {%1,%2,%3,%4};" ::"l"(p), "r"(a), "r"(b), "r"(c), "r"(d) : "memory");
}
__device__ __forceinline__ void st_relaxed4_if(bool pred, void* p, uint32_t a, uint32_t b, uint32_t c, uint32_t d) {
    asm volatile("{\n.reg .pred p;\nsetp.ne.u32 p, %5, 0;\n@p st.relaxed.gpu.global.v4.u32 [%0], {%1,%2,%3,%4};\n}"
                 ::"l"(p), "r"(a), "r"(b), "r"(c), "r"(d), "r"((uint32_t)pred) : "memory");
}
__device__ __forceinline__ void st_relaxed1(void* p, uint32_t a) {
    asm volatile("st.relaxed.gpu.global.u32 [%0], %1;" ::"l"(p), "r"(a) : "memory");
}
__device__ __forceinline__ bool nz4(const uint4& v) { return v.x != 0u && v.y != 0u && v.z != 0u && v.w != 0u; }
__device__ __forceinline__ uint32_t enc_bits(uint32_t b) { return b == 0u ? 0x80000000u : b; }
__device__ __forceinline__ uint32_t enc(float f, uint32_t tag) { return (__float_as_uint(f) & ~3u) | tag; }
__device__ __forceinline__ uint32_t tag_bad4(const uint4& v, uint32_t tmask) {
    uint32_t a;
    asm("lop3.b32 %0, %1, %2, %3, 0x7e;" : "=r"(a) : "r"(v.x), "r"(v.y), "r"(tmask));
    asm("lop3.b32 %0, %0, %1, %2, 0xf6;" : "+r"(a) : "r"(v.z), "r"(tmask));
    asm("lop3.b32 %0, %0, %1, %2, 0xf6;" : "+r"(a) : "r"(v.w), "r"(tmask));
    return a;
}

__device__ __forceinline__ uint4 lds128(uint32_t a) {
    uint4 v;
    asm volatile("ld.shared.v4.u32 {%0,%1,%2,%3}, [%4];" : "=r"(v.x), "=r"(v.y), "=r"(v.z), "=r"(v.w) : "r"(a) : "memory");
    return v;
}
__device__ __forceinline__ uint2 lds64(uint32_t a) {
    uint2 v;
    asm volatile("ld.shared.v2.u32 {%0,%1}, [%2];" : "=r"(v.x), "=r"(v.y) : "r"(a) : "memory");
    return v;
}
__device__ __forceinline__ void ldsm4(uint32_t (&r)[4], uint32_t a) {
    asm volatile("ldmatrix.sync.aligned.m8n8.x4.shared.b16 {%0,%1,%2,%3}, [%4];"
                 : "=r"(r[0]), "=r"(r[1]), "=r"(r[2]), "=r"(r[3]) : "r"(a) : "memory");
}
__device__ __forceinline__ void ldsm4t(uint32_t (&r)[4], uint32_t a) {
    asm volatile("ldmatrix.sync.aligned.m8n8.x4.trans.shared.b16 {%0,%1,%2,%3}, [%4];"
                 : "=r"(r[0]), "=r"(r[1]), "=r"(r[2]), "=r"(r[3]) : "r"(a) : "memory");
}
__device__ __forceinline__ void mma16816(float (&c)[4], const uint32_t (&a)[4], uint32_t b0, uint32_t b1) {
    asm volatile(
        "mma.sync.aligned.m16n8k16.row.col.f32.bf16.bf16.f32 {%0,%1,%2,%3}, {%4,%5,%6,%7}, {%8,%9}, {%0,%1,%2,%3};"
        : "+f"(c[0]), "+f"(c[1]), "+f"(c[2]), "+f"(c[3])
        : "r"(a[0]), "r"(a[1]), "r"(a[2]), "r"(a[3]), "r"(b0), "r"(b1));
}
__device__ __forceinline__ uint32_t movm(uint32_t a) {
    uint32_t d;
    asm volatile("movmatrix.sync.aligned.m8n8.trans.b16 %0, %1;" : "=r"(d) : "r"(a));
    return d;
}
__device__ __forceinline__ float bf_lo(uint32_t w) { return __uint_as_float(w << 16); }
__device__ __forceinline__ float bf_hi(uint32_t w) { return __uint_as_float(w & 0xffff0000u); }
__device__ __forceinline__ float bfr(float f) { return __bfloat162float(__float2bfloat16_rn(f)); }
__device__ __forceinline__ uint32_t pack_bf(float lo, float hi) {
    uint32_t r;
    asm("cvt.rn.bf16x2.f32 %0, %1, %2;" : "=r"(r) : "f"(hi), "f"(lo));
    return r;
}
__device__ __forceinline__ float ex2(float x) {
    float r;
    asm("ex2.approx.ftz.f32 %0, %1;" : "=f"(r) : "f"(x));
    return r;
}
__device__ __forceinline__ void fma8(float (&acc)[8], const uint4& w, float s) {
    acc[0] = fmaf(bf_lo(w.x), s, acc[0]); acc[1] = fmaf(bf_hi(w.x), s, acc[1]);
    acc[2] = fmaf(bf_lo(w.y), s, acc[2]); acc[3] = fmaf(bf_hi(w.y), s, acc[3]);
    acc[4] = fmaf(bf_lo(w.z), s, acc[4]); acc[5] = fmaf(bf_hi(w.z), s, acc[5]);
    acc[6] = fmaf(bf_lo(w.w), s, acc[6]); acc[7] = fmaf(bf_hi(w.w), s, acc[7]);
}
__device__ __forceinline__ void reduce_g8(float (&acc)[8]) {
#pragma unroll
    for (int o = 4; o <= 16; o <<= 1)
#pragma unroll
        for (int j = 0; j < 8; j++) acc[j] += __shfl_xor_sync(0xffffffffu, acc[j], o);
}

constexpr float LOG2E = 1.4426950408889634f;
constexpr float SM_SCALE = 0.08838834764831845f;
constexpr float M_EMPTY = -3.0e38f;

__global__ void __launch_bounds__(NTHREADS, 1) fused_decode_kernel(const __grid_constant__ Params P) {
    extern __shared__ uint8_t smem_raw[];
    uint8_t* sm = smem_raw + ((1024u - (smem_u32(smem_raw) & 1023u)) & 1023u);
    const uint32_t sb = smem_u32(sm);
    const int tid = threadIdx.x, lane = tid & 31, warp = tid >> 5;
    const int b = blockIdx.x;
    const uint32_t bar_full = sb + SM_BAR, bar_empty = bar_full + NSLOTS * 8;
    const uint32_t bar_flushed = bar_empty + NSLOTS * 8, bar_oready = bar_flushed + 32;
    volatile int* info = reinterpret_cast<volatile int*>(sm + SM_INFO);
    float* xs = reinterpret_cast<float*>(sm + SM_XS);
    float* small = reinterpret_cast<float*>(sm + SM_SMALL);
    float* hs = small;
    float* os = small + 32;
    float* tmp = small + 64;

    if (tid == NCONS && b < NQ_CTAS) {
#pragma unroll
        for (int i = 0; i < NINF; i++) mbar_init(bar_full + 8 * i, 1);
        asm volatile("fence.mbarrier_init.release.cluster;" ::: "memory");
#pragma unroll
        for (int i = 0; i < NINF; i++) {
            mbar_expect_tx(bar_full + 8 * i, SLOT_BYTES);
            tma2(&P.q, 32 * b, 256 * i, sb + i * SLOT_BYTES, bar_full + 8 * i);
        }
    }

    uint32_t tag;
    asm volatile("ld.relaxed.gpu.global.u32 %0, [%1];" : "=r"(tag) : "l"(&g_state[0]) : "memory");
    tag = (tag & 1u) ^ 1u;

    if (warp == 4) {
        unsigned nA = 0, nB = 0;
        if (lane == 0) {
#pragma unroll
            for (int i = 0; i < NSLOTS; i++) {
                if (i >= NINF || b >= NQ_CTAS) mbar_init(bar_full + 8 * i, 1);
                mbar_init(bar_empty + 8 * i, 4);
            }
#pragma unroll
            for (int i = 0; i < 8; i++) mbar_init(bar_flushed + 8 * i, 1);
            asm volatile("fence.mbarrier_init.release.cluster;" ::: "memory");
            asm volatile("prefetch.tensormap [%0];" ::"l"(&P.k) : "memory");
            asm volatile("prefetch.tensormap [%0];" ::"l"(&P.v) : "memory");
            asm volatile("prefetch.tensormap [%0];" ::"l"(&P.g) : "memory");
            asm volatile("prefetch.tensormap [%0];" ::"l"(&P.u) : "memory");
        }
        __syncwarp();
        bar_arrive(1, NTHREADS);
        if (lane == 0) {
            uint64_t pol;
            asm volatile("createpolicy.fractional.L2::evict_first.b64 %0, 1.0;" : "=l"(pol));
            const __nv_bfloat16* wd_src = P.wd + (size_t)b * 32 * D_MODEL;
            const __nv_bfloat16* wo_src = P.wo + (size_t)b * 8 * D_MODEL;
            asm volatile("" : "+l"(wd_src), "+l"(wo_src));
            unsigned* const ctr = &g_state[1 + tag];
            if (b == 0) g_state[2 - tag] = 0u;
            int slot = b < NQ_CTAS ? NINF : 0, lag = 0, cnt = slot, landed = 0, marker = -1;
            uint32_t ph = 1, lag_ph = 0;
            auto acquire = [&](int tile_info) {
                mbar_wait(bar_empty + 8 * slot, ph);
                info[slot] = tile_info;
                mbar_expect_tx(bar_full + 8 * slot, SLOT_BYTES);
                while (cnt - landed >= NINF + (landed <= marker ? 1 : 0)) {
                    mbar_wait(bar_full + 8 * lag, lag_ph);
                    if (++lag == NSLOTS) { lag = 0; lag_ph ^= 1; }
                    landed++;
                }
                cnt++;
            };
            auto advance = [&]() { if (++slot == NSLOTS) { slot = 0; ph ^= 1; } };
            if (b < NQ_CTAS) {
                const int npre = b < NF_CTAS ? 4 + 2 * FFN_PRE : 4;
                static_assert(NINF <= 4, "prologue issues Wq boxes only");
                if (npre - 3 < NINF) {
                    nA = NSTATIC + atomicAdd(ctr, 1u);
                    nB = NSTATIC + atomicAdd(ctr, 1u);
                }
#pragma unroll 1
                for (int i = NINF; i < npre; i++) {
                    const CUtensorMap* mp = i < 4 ? &P.q : ((i & 1) ? &P.u : &P.g);
                    const int row = 256 * (i < 4 ? i : ((i - 4) >> 1));
                    acquire(0);
                    tma2(mp, 32 * b, row, sb + slot * SLOT_BYTES, bar_full + 8 * slot);
                    advance();
                    if (i == npre - 3) {
                        nA = NSTATIC + atomicAdd(ctr, 1u);
                        nB = NSTATIC + atomicAdd(ctr, 1u);
                    }
                }
            } else {
                nA = b - NQ_CTAS;
                nB = nA + (NCTA - NQ_CTAS);
            }
            unsigned tA = globaltimer_lo(), tB = tA, tx;
            auto issue_tile = [&](unsigned t) {
                acquire((int)t);
                tma3(&P.k, (int)t * TILE_KEYS, sb + slot * SLOT_BYTES, bar_full + 8 * slot, pol);
                advance();
                acquire(0);
                tma3(&P.v, (int)t * TILE_KEYS, sb + slot * SLOT_BYTES, bar_full + 8 * slot, pol);
                advance();
            };
#pragma unroll 1
            while (true) {
                if (nA >= (unsigned)NTILES) { tx = tA - 10u * (nA - NTILES); break; }
                issue_tile(nA);
                tA = globaltimer_lo();
                nA = NSTATIC + atomicAdd(ctr, 1u);
                if (nB >= (unsigned)NTILES) { tx = tB - 10u * (nB - NTILES); break; }
                issue_tile(nB);
                tB = globaltimer_lo();
                nB = NSTATIC + atomicAdd(ctr, 1u);
            }
            info[NSLOTS] = (int)tx;
            mbar_wait(bar_empty + 8 * slot, ph);
            info[slot] = -1;
            mbar_arrive(bar_full + 8 * slot);
            advance();
            marker = cnt++;
            if (b < NQ_CTAS) {
                constexpr int NGU = 2 * (4 - FFN_PRE);
#pragma unroll 1
                for (int j = b < NF_CTAS ? 0 : NGU + 4; j < NGU + 8; j++) {
                    const __nv_bfloat16* src = j < NGU + 4 ? wd_src + (j - NGU) * 8 * D_MODEL
                                                           : wo_src + (size_t)(j - NGU - 4) * 1024 * D_MODEL;
                    acquire(0);
                    if (j < NGU) tma2((j & 1) ? &P.u : &P.g, 32 * b, 256 * (FFN_PRE + (j >> 1)), sb + slot * SLOT_BYTES, bar_full + 8 * slot);
                    else bulk1(src, sb + slot * SLOT_BYTES, bar_full + 8 * slot, pol);
                    advance();
                }
            }
        }
        return;
    }


    if (warp == 5) {
        if (b >= NQ_CTAS) { bar_arrive(1, NTHREADS); return; }
        {
            uint4 xv[4];
#pragma unroll
            for (int i = 0; i < 4; i++) xv[i] = ldg_stream(P.x + (i * 32 + lane) * 8);
            float xf[32];
#pragma unroll
            for (int i = 0; i < 4; i++) {
                xf[8 * i + 0] = bf_lo(xv[i].x); xf[8 * i + 1] = bf_hi(xv[i].x);
                xf[8 * i + 2] = bf_lo(xv[i].y); xf[8 * i + 3] = bf_hi(xv[i].y);
                xf[8 * i + 4] = bf_lo(xv[i].z); xf[8 * i + 5] = bf_hi(xv[i].z);
                xf[8 * i + 6] = bf_lo(xv[i].w); xf[8 * i + 7] = bf_hi(xv[i].w);
            }
            float s = 0.f;
#pragma unroll
            for (int i = 0; i < 32; i++) s += xf[i];
#pragma unroll
            for (int o = 16; o; o >>= 1) s += __shfl_xor_sync(0xffffffffu, s, o);
            const float mean = s * (1.0f / D_MODEL);
            float vs = 0.f;
#pragma unroll
            for (int i = 0; i < 32; i++) { const float d = xf[i] - mean; vs = fmaf(d, d, vs); }
#pragma unroll
            for (int o = 16; o; o >>= 1) vs += __shfl_xor_sync(0xffffffffu, vs, o);
            const float mean_b = bfr(mean);
            const float var_b = bfr(vs * (1.0f / D_MODEL));
            const float den = bfr(__fsqrt_rn(bfr(var_b + 1e-5f)));
#pragma unroll
            for (int i = 0; i < 4; i++) {
                float y[8];
#pragma unroll
                for (int j = 0; j < 8; j++) y[j] = bfr(__fdiv_rn(bfr(xf[8 * i + j] - mean_b), den));
                float4* dst = reinterpret_cast<float4*>(xs + (i * 32 + lane) * 8);
                dst[0] = make_float4(y[0], y[1], y[2], y[3]);
                dst[1] = make_float4(y[4], y[5], y[6], y[7]);
            }
        }
        const uint2 xres = *reinterpret_cast<const uint2*>(P.x + b * 8 + (lane & 1) * 4);
        bar_sync(1, NTHREADS);

        const uint32_t* fsrc = g_part + (size_t)(FIN_G * NQ_CTAS + b) * NCTA * 8;
        __nv_bfloat16* out_dst = P.out + b * 8 + lane * 4;
        const uint32_t* part_src = g_part + (size_t)b * NCTA * 8 + lane * 4;
        asm volatile("" : "+l"(out_dst), "+l"(fsrc), "+l"(part_src));
        float r0 = lane < 2 ? bf_lo(xres.x) : 0.f, r1 = lane < 2 ? bf_hi(xres.x) : 0.f;
        float r2 = lane < 2 ? bf_lo(xres.y) : 0.f, r3 = lane < 2 ? bf_hi(xres.y) : 0.f;
        unsigned fpend = 0xffu;
        uint32_t tmask = tag, fmask = tag | 2u;
        asm volatile("" : "+r"(tmask), "+r"(fmask));
        auto poll_fin = [&]() {
            uint4 fv[8];
#pragma unroll
            for (int i = 0; i < 8; i++)
                fv[i] = ld_relaxed4(fsrc + ((fpend & (1u << i)) ? (uint32_t)(lane * 4 + i * 128) : 0u));
            uint32_t badm = 0u;
#pragma unroll
            for (int i = 0; i < 8; i++) badm |= ((tag_bad4(fv[i], fmask) & 3u) ? 1u : 0u) << i;
            const uint32_t fresh = fpend & ~badm;
            fpend &= badm;
#pragma unroll
            for (int i = 0; i < 8; i++) {
                asm volatile("{\n.reg .pred p;\n.reg .b32 t;\nand.b32 t, %8, %9;\nsetp.ne.u32 p, t, 0;\n"
                             "@p add.f32 %0, %0, %4;\n@p add.f32 %1, %1, %5;\n@p add.f32 %2, %2, %6;\n@p add.f32 %3, %3, %7;\n}"
                             : "+f"(r0), "+f"(r1), "+f"(r2), "+f"(r3)
                             : "f"(__uint_as_float(fv[i].x)), "f"(__uint_as_float(fv[i].y)),
                               "f"(__uint_as_float(fv[i].z)), "f"(__uint_as_float(fv[i].w)), "r"(fresh), "r"(1u << i));
            }
        };
#pragma unroll 1
        for (int g = 0; g < HKV; g++) {
            const uint32_t* pp = part_src + (size_t)(g == HKV - 1 ? LAST_G : g) * NQ_CTAS * NCTA * 8;
            const uint32_t* pp8 = lane < 2 * (NCTA - 128) ? part_src + (size_t)g * NQ_CTAS * NCTA * 8 + 8 * 128 : pp;
            const uint32_t want = g == HKV - 1 ? fmask : tmask;
            uint4 pv[9];
            bool pend = true;
            auto poll_part = [&]() {
#pragma unroll
                for (int i = 0; i < 8; i++) pv[i] = ld_relaxed4(pp + i * 128);
                pv[8] = ld_relaxed4(pp8);
                uint32_t bad = 0u;
#pragma unroll
                for (int i = 0; i < 9; i++) bad |= tag_bad4(pv[i], want);
                pend = bad & 3u;
            };
            mbar_wait(bar_flushed + 8 * g, 0);
            {
                const unsigned t_start = g < HKV - 1 ? globaltimer_lo() : (unsigned)info[NSLOTS];
                if (g == HKV - 1) poll_fin();
                const unsigned delay = g < HKV - 1 ? COMB_DELAY_NS : LAST_DELAY_NS;
                while (globaltimer_lo() - t_start < delay) __nanosleep(100);
            }
            unsigned it = 0;
            while (true) {
                poll_part();
                if (!pend) break;
                if (++it > SPIN_LIMIT) __trap();
            }
            __syncwarp();
            if (g == 0) {
                if (lane < 16) g_q[16 * b + lane] = 0u;
                if (b == 0 && lane == 0) st_relaxed1(&g_state[0], tag);
            }
            if (lane >= 2 * (NCTA - 128)) pv[8] = make_uint4(0u, __float_as_uint(M_EMPTY), 0u, 0u);
            const bool odd = lane & 1;
            float M = M_EMPTY;
#pragma unroll
            for (int i = 0; i < 9; i++) M = fmaxf(M, odd ? __uint_as_float(pv[i].y) : M_EMPTY);
#pragma unroll
            for (int of = 16; of; of >>= 1) M = fmaxf(M, __shfl_xor_sync(0xffffffffu, M, of));
            float r[8], L = 0.f;
#pragma unroll
            for (int j = 0; j < 8; j++) r[j] = 0.f;
#pragma unroll
            for (int i = 0; i < 9; i++) {
                const float w = odd ? ex2((__uint_as_float(pv[i].y) - M) * LOG2E) : 0.f;
                L = fmaf(w, odd ? __uint_as_float(pv[i].z) : 0.f, L);
                const float c = __shfl_xor_sync(0xffffffffu, w * __uint_as_float(odd ? pv[i].x : 0u), 1);
                r[0] = fmaf(c, (float)((int)(pv[i].x << 15) >> 17), r[0]); r[1] = fmaf(c, (float)((int)pv[i].x >> 17), r[1]);
                r[2] = fmaf(c, (float)((int)(pv[i].y << 15) >> 17), r[2]); r[3] = fmaf(c, (float)((int)pv[i].y >> 17), r[3]);
                r[4] = fmaf(c, (float)((int)(pv[i].z << 15) >> 17), r[4]); r[5] = fmaf(c, (float)((int)pv[i].z >> 17), r[5]);
                r[6] = fmaf(c, (float)((int)(pv[i].w << 15) >> 17), r[6]); r[7] = fmaf(c, (float)((int)pv[i].w >> 17), r[7]);
            }
            const bool u16 = lane & 16, u8 = lane & 8, u4 = lane & 4;
#pragma unroll
            for (int j = 0; j < 4; j++) {
                const float send = u16 ? r[j] : r[j + 4], keep = u16 ? r[j + 4] : r[j];
                r[j] = keep + __shfl_xor_sync(0xffffffffu, send, 16);
            }
#pragma unroll
            for (int j = 0; j < 2; j++) {
                const float send = u8 ? r[j] : r[j + 2], keep = u8 ? r[j + 2] : r[j];
                r[j] = keep + __shfl_xor_sync(0xffffffffu, send, 8);
            }
            {
                const float send = u4 ? r[0] : r[1], keep = u4 ? r[1] : r[0];
                r[0] = keep + __shfl_xor_sync(0xffffffffu, send, 4);
            }
            r[0] += __shfl_xor_sync(0xffffffffu, r[0], 2);
#pragma unroll
            for (int of = 16; of; of >>= 1) L += __shfl_xor_sync(0xffffffffu, L, of);
            if ((lane & 3) == 0) os[g * 8 + (lane >> 2)] = bfr(r[0] / L);
            __syncwarp();
            if (lane == 0) mbar_arrive(bar_oready + 8 * g);
        }
        bar_sync(3, NCONS + 32);
        {
            unsigned it = 0;
            while (true) {
                poll_fin();
                if (__all_sync(0xffffffffu, fpend == 0u)) break;
                if (++it > SPIN_LIMIT) __trap();
            }
#pragma unroll
            for (int of = 2; of <= 16; of <<= 1) {
                r0 += __shfl_xor_sync(0xffffffffu, r0, of); r1 += __shfl_xor_sync(0xffffffffu, r1, of);
                r2 += __shfl_xor_sync(0xffffffffu, r2, of); r3 += __shfl_xor_sync(0xffffffffu, r3, of);
            }
            if (lane < 2)
                asm volatile("st.global.v2.u32 [%0], {%1,%2};" ::"l"(out_dst), "r"(pack_bf(r0, r1)), "r"(pack_bf(r2, r3)) : "memory");
        }
        return;
    }

    float* red = reinterpret_cast<float*>(sm + SM_RED);
    uint32_t* qs = reinterpret_cast<uint32_t*>(sm + SM_QS);
    const int g8 = lane >> 2, c4 = lane & 3;

    bar_sync(1, NTHREADS);

    int slot = 0;
    uint32_t ph = 0;
    auto advance = [&]() { if (++slot == NSLOTS) { slot = 0; ph ^= 1; } };
    auto release = [&]() { __syncwarp(); if (lane == 0) mbar_arrive(bar_empty + 8 * slot); advance(); };
    auto box = [&](float (&acc)[8], int i) {
        float xr[8];
#pragma unroll
        for (int j = 0; j < 8; j++) xr[j] = xs[256 * i + 32 * j + (tid >> 2)];
        mbar_wait(bar_full + 8 * slot, ph);
#pragma unroll
        for (int j = 0; j < 8; j++) fma8(acc, lds128(sb + slot * SLOT_BYTES + j * 2048 + tid * 16), xr[j]);
        release();
    };

    if (b < NQ_CTAS) {
        float acc[8];
#pragma unroll
        for (int j = 0; j < 8; j++) acc[j] = 0.f;
#pragma unroll 1
        for (int i = 0; i < 4; i++) box(acc, i);
        reduce_g8(acc);
        if (g8 == 0) {
#pragma unroll
            for (int j = 0; j < 8; j++) tmp[warp * 32 + c4 * 8 + j] = acc[j];
        }
        cons_sync();
        if (tid < 16) {
            const float* tq = tmp;
            const float q0 = tq[2 * tid] + tq[32 + 2 * tid] + tq[64 + 2 * tid] + tq[96 + 2 * tid];
            const float q1 = tq[2 * tid + 1] + tq[33 + 2 * tid] + tq[65 + 2 * tid] + tq[97 + 2 * tid];
            st_relaxed1(&g_q[16 * b + tid], enc_bits(pack_bf(q0, q1)));
        }
    }

    float ag[8], au[8];
#pragma unroll
    for (int j = 0; j < 8; j++) { ag[j] = 0.f; au[j] = 0.f; }
    auto finish_hidden = [&]() {
        reduce_g8(ag);
        reduce_g8(au);
        if (g8 == 0) {
#pragma unroll
            for (int j = 0; j < 8; j++) {
                tmp[128 + warp * 32 + c4 * 8 + j] = ag[j];
                tmp[256 + warp * 32 + c4 * 8 + j] = au[j];
            }
        }
        cons_sync();
        if (tid < 32) {
            const float gg = bfr(tmp[128 + tid] + tmp[160 + tid] + tmp[192 + tid] + tmp[224 + tid]);
            const float uu = bfr(tmp[256 + tid] + tmp[288 + tid] + tmp[320 + tid] + tmp[352 + tid]);
            const float inner = 0.7978845608028654f * (gg + 0.044715f * gg * gg * gg);
            const float ge = bfr(0.5f * gg * (1.0f + tanhf(inner)));
            hs[tid] = bfr(ge * uu);
        }
    };
    if (b < NF_CTAS) {
#pragma unroll 1
        for (int i = 0; i < FFN_PRE; i++) { box(ag, i); box(au, i); }
        if (FFN_PRE == 4) finish_hidden();
    }

    {
        uint4 qv[4];
        unsigned it = 0;
        while (true) {
#pragma unroll
            for (int i = 0; i < 4; i++) qv[i] = ld_relaxed4(&g_q[(i * NCONS + tid) * 4]);
            if (nz4(qv[0]) && nz4(qv[1]) && nz4(qv[2]) && nz4(qv[3])) break;
            if (++it > SPIN_LIMIT) __trap();
        }
#pragma unroll
        for (int i = 0; i < 4; i++) {
            const int w = (i * NCONS + tid) * 4;
            *reinterpret_cast<uint4*>(&qs[(w >> 6) * QS_STRIDE + (w & 63)]) = qv[i];
        }
        cons_sync();
    }

    uint32_t qf[16];
    float o[8][4];
    float m0, m1, l0, l1;
    auto load_q = [&](int g) {
#pragma unroll
        for (int ks = 0; ks < 8; ks++) {
            qf[2 * ks] = qs[(g * 8 + g8) * QS_STRIDE + ks * 8 + c4];
            qf[2 * ks + 1] = qs[(g * 8 + g8) * QS_STRIDE + ks * 8 + 4 + c4];
        }
    };
    auto reset_acc = [&]() {
#pragma unroll
        for (int i = 0; i < 8; i++) { o[i][0] = 0.f; o[i][1] = 0.f; o[i][2] = 0.f; o[i][3] = 0.f; }
        m0 = M_EMPTY; m1 = M_EMPTY; l0 = 0.f; l1 = 0.f;
    };
    uint32_t* part_dst = g_part + ((size_t)((tid >> 4) * 16 + ((tid & 15) >> 1)) * NCTA + b) * 8 + (tid & 1) * 4;
    asm volatile("" : "+l"(part_dst));
    auto flush = [&](int g) {
#pragma unroll
        for (int of = 4; of <= 16; of <<= 1) {
            l0 += __shfl_xor_sync(0xffffffffu, l0, of);
            l1 += __shfl_xor_sync(0xffffffffu, l1, of);
        }
        cons_sync();
        float* rw = red + warp * 8 * RED_STRIDE;
#pragma unroll
        for (int i = 0; i < 8; i++) {
            rw[(2 * c4) * RED_STRIDE + 16 * i + g8] = o[i][0];
            rw[(2 * c4 + 1) * RED_STRIDE + 16 * i + g8] = o[i][1];
            rw[(2 * c4) * RED_STRIDE + 16 * i + 8 + g8] = o[i][2];
            rw[(2 * c4 + 1) * RED_STRIDE + 16 * i + 8 + g8] = o[i][3];
        }
        if (g8 == 0) {
            tmp[warp * 8 + 2 * c4] = m0; tmp[warp * 8 + 2 * c4 + 1] = m1;
            tmp[32 + warp * 8 + 2 * c4] = l0; tmp[32 + warp * 8 + 2 * c4 + 1] = l1;
        }
        cons_sync();
        const int h = tid >> 4, i16 = tid & 15;
        float mw[4], M = M_EMPTY;
#pragma unroll
        for (int w = 0; w < 4; w++) { mw[w] = tmp[w * 8 + h]; M = fmaxf(M, mw[w]); }
        float L = 0.f, r[8];
#pragma unroll
        for (int j = 0; j < 8; j++) r[j] = 0.f;
#pragma unroll
        for (int w = 0; w < 4; w++) {
            const float sc = ex2((mw[w] - M) * LOG2E);
            L = fmaf(sc, tmp[32 + w * 8 + h], L);
            const float4 a = *reinterpret_cast<const float4*>(red + (w * 8 + h) * RED_STRIDE + 4 * i16);
            const float4 c = *reinterpret_cast<const float4*>(red + (w * 8 + h) * RED_STRIDE + 64 + 4 * i16);
            r[0] = fmaf(sc, a.x, r[0]); r[1] = fmaf(sc, a.y, r[1]); r[2] = fmaf(sc, a.z, r[2]); r[3] = fmaf(sc, a.w, r[3]);
            r[4] = fmaf(sc, c.x, r[4]); r[5] = fmaf(sc, c.y, r[5]); r[6] = fmaf(sc, c.z, r[6]); r[7] = fmaf(sc, c.w, r[7]);
        }
        uint32_t* dst = part_dst + (size_t)((g == HKV - 1 && b < NQ_CTAS) ? LAST_G : g) * NQ_CTAS * NCTA * 8;
        if (g >= 2 && b < NQ_CTAS) mbar_wait(bar_oready + 8 * (g - 1), 0);
        const uint32_t ptag = g == HKV - 1 ? (tag | 2u) : tag;
#pragma unroll
        for (int k = 0; k < 2; k++) {
            float amax = fmaxf(fmaxf(fabsf(r[4 * k]), fabsf(r[4 * k + 1])), fmaxf(fabsf(r[4 * k + 2]), fabsf(r[4 * k + 3])));
            amax = fmaxf(amax, __shfl_xor_sync(0xffffffffu, amax, 1));
            const float inv = amax > 0.f ? 16383.f / amax : 0.f;
            const uint32_t w0 = ((uint32_t)(__float2int_rn(r[4 * k] * inv) & 0x7fff) << 2) |
                                ((uint32_t)__float2int_rn(r[4 * k + 1] * inv) << 17) | ptag;
            const uint32_t w1 = ((uint32_t)(__float2int_rn(r[4 * k + 2] * inv) & 0x7fff) << 2) |
                                ((uint32_t)__float2int_rn(r[4 * k + 3] * inv) << 17) | ptag;
            const uint32_t p0 = __shfl_xor_sync(0xffffffffu, w0, 1), p1 = __shfl_xor_sync(0xffffffffu, w1, 1);
            const bool o1 = i16 & 1;
            st_relaxed4(dst + (size_t)k * 8 * NCTA * 8,
                        o1 ? enc(amax * (1.f / 16383.f), ptag) : w0, o1 ? enc(M, ptag) : w1,
                        o1 ? enc(L, ptag) : p0, o1 ? ptag : p1);
        }
        if (tid == 0) mbar_arrive(bar_flushed + 8 * g);
        reset_acc();
    };

    int cur_g = 0;
    load_q(0);
    reset_acc();
    const int krow = warp * 16 + (lane & 7) + ((lane >> 3) & 1) * 8;
    const uint32_t k_off = krow * 128;
    const int k_hi = lane >> 4;
    const int vrow = warp * 16 + (lane & 7) + (lane >> 4) * 8;
    const uint32_t v_off = vrow * 128;
    const int v_hi = (lane >> 3) & 1;
    const int sw = lane & 7;
#pragma unroll 1
    while (true) {
        mbar_wait(bar_full + 8 * slot, ph);
        const int t = info[slot];
        const int g = t < 0 ? HKV : t >> TILES_PER_GROUP_LOG2;
        if (g != cur_g) {
            while (cur_g < g) { flush(cur_g); cur_g++; }
            if (t < 0) { release(); break; }
            load_q(g);
        }
        float sa[4] = {0.f, 0.f, 0.f, 0.f}, sc2[4] = {0.f, 0.f, 0.f, 0.f};
        {
            const uint32_t base = sb + slot * SLOT_BYTES + k_off;
            uint32_t a[8][4];
#pragma unroll
            for (int ks = 0; ks < 8; ks++)
                ldsm4(a[ks], base + (ks >> 2) * 8192 + ((((2 * ks) & 7) + k_hi) ^ sw) * 16);
#pragma unroll
            for (int ks = 0; ks < 8; ks += 2) {
                mma16816(sa, a[ks], qf[2 * ks], qf[2 * ks + 1]);
                mma16816(sc2, a[ks + 1], qf[2 * ks + 2], qf[2 * ks + 3]);
            }
        }
        release();
        float s[4];
#pragma unroll
        for (int j = 0; j < 4; j++) s[j] = bfr(bfr(sa[j] + sc2[j]) * SM_SCALE);
        float mx0 = fmaxf(s[0], s[2]), mx1 = fmaxf(s[1], s[3]);
        if (__any_sync(0xffffffffu, mx0 > m0 || mx1 > m1)) {
#pragma unroll
            for (int of = 4; of <= 16; of <<= 1) {
                mx0 = fmaxf(mx0, __shfl_xor_sync(0xffffffffu, mx0, of));
                mx1 = fmaxf(mx1, __shfl_xor_sync(0xffffffffu, mx1, of));
            }
            mx0 = fmaxf(mx0, m0);
            mx1 = fmaxf(mx1, m1);
            const float a0 = ex2((m0 - mx0) * LOG2E), a1 = ex2((m1 - mx1) * LOG2E);
            m0 = mx0; m1 = mx1;
            l0 *= a0; l1 *= a1;
#pragma unroll
            for (int i = 0; i < 8; i++) { o[i][0] *= a0; o[i][1] *= a1; o[i][2] *= a0; o[i][3] *= a1; }
        }
        const float p0 = ex2((s[0] - m0) * LOG2E), p1 = ex2((s[1] - m1) * LOG2E);
        const float p2 = ex2((s[2] - m0) * LOG2E), p3 = ex2((s[3] - m1) * LOG2E);
        l0 += p0 + p2;
        l1 += p1 + p3;
        const uint32_t pb0 = movm(pack_bf(p0, p1)), pb1 = movm(pack_bf(p2, p3));
        mbar_wait(bar_full + 8 * slot, ph);
        {
            const uint32_t base = sb + slot * SLOT_BYTES + v_off;
            uint32_t a[8][4];
#pragma unroll
            for (int mt = 0; mt < 8; mt++)
                ldsm4t(a[mt], base + (mt >> 2) * 8192 + ((((2 * mt) & 7) + v_hi) ^ sw) * 16);
#pragma unroll
            for (int mt = 0; mt < 8; mt++) mma16816(o[mt], a[mt], pb0, pb1);
        }
        release();
    }
    if (b >= NQ_CTAS) return;

    uint32_t* fin_dst = g_part + ((size_t)(FIN_G * NQ_CTAS + (tid >> 1)) * NCTA + b) * 8 + (tid & 1) * 4;
    const uint32_t ftag = tag | 2u;
    asm volatile("" : "+l"(fin_dst));

    float acc[8];
#pragma unroll
    for (int j = 0; j < 8; j++) acc[j] = 0.f;
    auto gemv_chunk = [&](const float* vec) {
        const float4 v0 = *reinterpret_cast<const float4*>(vec), v1 = *reinterpret_cast<const float4*>(vec + 4);
        const float vr[8] = {v0.x, v0.y, v0.z, v0.w, v1.x, v1.y, v1.z, v1.w};
        mbar_wait(bar_full + 8 * slot, ph);
        const uint32_t base = sb + slot * SLOT_BYTES + tid * 8;
#pragma unroll
        for (int r = 0; r < 8; r++) {
            const uint2 lo = lds64(base + r * 2048), hi = lds64(base + r * 2048 + 1024);
            fma8(acc, make_uint4(lo.x, lo.y, hi.x, hi.y), vr[r]);
        }
        advance();
    };
    if (b < NF_CTAS) {
        if (FFN_PRE < 4) {
#pragma unroll 1
            for (int i = FFN_PRE; i < 4; i++) { box(ag, i); box(au, i); }
            finish_hidden();
            cons_sync();
        }
#pragma unroll 1
        for (int i = 0; i < 4; i++) gemv_chunk(hs + 8 * i);
    }
#pragma unroll 1
    for (int i = 0; i < 4; i++) {
        mbar_wait(bar_oready + 8 * i, 0);
        gemv_chunk(os + 8 * i);
        st_relaxed4_if(i == 3, fin_dst, enc(acc[0], ftag), enc(acc[1], ftag), enc(acc[2], ftag), enc(acc[3], ftag));
        st_relaxed4_if(i == 3, fin_dst + (size_t)64 * NCTA * 8, enc(acc[4], ftag), enc(acc[5], ftag), enc(acc[6], ftag), enc(acc[7], ftag));
    }
    bar_arrive(3, NCONS + 32);
}

typedef CUresult (*EncodeFn)(CUtensorMap*, CUtensorMapDataType, cuuint32_t, void*, const cuuint64_t*, const cuuint64_t*,
                             const cuuint32_t*, const cuuint32_t*, CUtensorMapInterleave, CUtensorMapSwizzle,
                             CUtensorMapL2promotion, CUtensorMapFloatOOBfill);

void make_kv_map(EncodeFn enc_fn, CUtensorMap* m, void* p) {
    cuuint64_t gd[3] = {64, (cuuint64_t)HKV * SK, 2};
    cuuint64_t gs[2] = {256, 128};
    cuuint32_t bd[3] = {64, TILE_KEYS, 2};
    cuuint32_t es[3] = {1, 1, 1};
    enc_fn(m, CU_TENSOR_MAP_DATA_TYPE_BFLOAT16, 3, p, gd, gs, bd, es, CU_TENSOR_MAP_INTERLEAVE_NONE,
           CU_TENSOR_MAP_SWIZZLE_128B, CU_TENSOR_MAP_L2_PROMOTION_L2_256B, CU_TENSOR_MAP_FLOAT_OOB_FILL_NONE);
}
void make_w_map(EncodeFn enc_fn, CUtensorMap* m, void* p, int cols) {
    cuuint64_t gd[2] = {(cuuint64_t)cols, D_MODEL};
    cuuint64_t gs[1] = {(cuuint64_t)cols * 2};
    cuuint32_t bd[2] = {32, 256};
    cuuint32_t es[2] = {1, 1};
    enc_fn(m, CU_TENSOR_MAP_DATA_TYPE_BFLOAT16, 2, p, gd, gs, bd, es, CU_TENSOR_MAP_INTERLEAVE_NONE,
           CU_TENSOR_MAP_SWIZZLE_NONE, CU_TENSOR_MAP_L2_PROMOTION_L2_256B, CU_TENSOR_MAP_FLOAT_OOB_FILL_NONE);
}

}

extern "C" void kernel_launch(void* const* d_in, const int* in_sizes, int n_in, void* d_out, int out_size) {
    (void)in_sizes; (void)n_in; (void)out_size;
    static EncodeFn enc_fn = nullptr;
    if (!enc_fn) {
        cudaDriverEntryPointQueryResult qr;
        cudaGetDriverEntryPoint("cuTensorMapEncodeTiled", (void**)&enc_fn, cudaEnableDefault, &qr);
        cudaFuncSetAttribute(fused_decode_kernel, cudaFuncAttributeMaxDynamicSharedMemorySize, SMEM_BYTES);
    }
    Params P;
    make_kv_map(enc_fn, &P.k, d_in[1]);
    make_kv_map(enc_fn, &P.v, d_in[2]);
    make_w_map(enc_fn, &P.q, d_in[3], 4096);
    make_w_map(enc_fn, &P.g, d_in[6], DFF);
    make_w_map(enc_fn, &P.u, d_in[7], DFF);
    P.x = (const __nv_bfloat16*)d_in[0];
    P.wo = (const __nv_bfloat16*)d_in[4];
    P.wd = (const __nv_bfloat16*)d_in[8];
    P.out = (__nv_bfloat16*)d_out;
    void* args[] = {&P};
    cudaLaunchCooperativeKernel((const void*)fused_decode_kernel, dim3(NCTA), dim3(NTHREADS), args, SMEM_BYTES,
                                cudaStreamPerThread);
}
```
